```python
import torch

def _softmax(x, axis=-1):
    return torch.softmax(x, dim=axis)
def _gelu(x):
    return torch.nn.functional.gelu(x, approximate="tanh")
def _silu(x):
    return torch.nn.functional.silu(x)
def _sigmoid(x):
    return torch.sigmoid(x)
def _layernorm(x, axis=-1, eps=1e-5):
    m = x.mean(dim=axis, keepdim=True)
    v = x.var(dim=axis, keepdim=True, unbiased=False)
    return (x - m) / torch.sqrt(v + eps)
def _scatter_add(tgt, idx, src, axis=0):
    return tgt.clone().index_add_(axis, idx, src)
def _segment_sum(src, seg, n):
    out = torch.zeros((n,) + src.shape[1:], dtype=src.dtype)
    return out.index_add_(0, seg, src)
def _pad(x, pw):
    flat = tuple(v for pair in reversed(pw) for v in pair)
    return torch.nn.functional.pad(x, flat)

kernel_name = 'concat_heads__mha_block_cached__gqa_block_cached__near_ridge'

def setup_inputs():

    _w = (lambda a: (lambda t: t.to(torch.bfloat16) if t.is_floating_point() else t)(torch.as_tensor(a)))
    def _A_setup():
        B, Sq, D = 8, 128, 640
        H, Sk, Dh = 32, 1024, 192
        return {
            "x": _w((lambda *s: torch.randn(*s, dtype=torch.bfloat16) * 0.8)(B, Sq, D)),
            "k_cache": _w((lambda *s: torch.randn(*s, dtype=torch.bfloat16) * 0.8)(B, H, Sk, Dh)),
            "v_cache": _w((lambda *s: torch.randn(*s, dtype=torch.bfloat16) * 0.05)(B, H, Sk, Dh)),
            "wq": _w((lambda *s: torch.randn(*s, dtype=torch.bfloat16) * 0.8)(D, H * Dh) * (D ** -0.5)),
            "wo": _w((lambda *s: torch.randn(*s, dtype=torch.bfloat16) * 0.05)(H * Dh, D) * ((H * Dh) ** -0.5)),
        }
    _A_in = _A_setup()

    def _B_setup():
        B, Sq, D = 8, 128, 640
        Hq, Hkv, Sk, Dh = 32, 32, 1024, 192
        assert Hq % Hkv == 0, (Hq, Hkv)
        return {
            "x": _w((lambda *s: torch.randn(*s, dtype=torch.bfloat16) * 0.8)(B, Sq, D)),
            "k_cache": _w((lambda *s: torch.randn(*s, dtype=torch.bfloat16) * 0.8)(B, Hkv, Sk, Dh)),
            "v_cache": _w((lambda *s: torch.randn(*s, dtype=torch.bfloat16) * 0.05)(B, Hkv, Sk, Dh)),
            "wq": _w((lambda *s: torch.randn(*s, dtype=torch.bfloat16) * 0.8)(D, Hq * Dh) * (D ** -0.5)),
            "wo": _w((lambda *s: torch.randn(*s, dtype=torch.bfloat16) * 0.05)(Hq * Dh, D) * ((Hq * Dh) ** -0.5)),
        }
    _B_in = _B_setup()

    return {
        "A_x": _A_in["x"],
        "A_k_cache": _A_in["k_cache"],
        "A_v_cache": _A_in["v_cache"],
        "A_wq": _A_in["wq"],
        "A_wo": _A_in["wo"],
        "B_x": _B_in["x"],
        "B_k_cache": _B_in["k_cache"],
        "B_v_cache": _B_in["v_cache"],
        "B_wq": _B_in["wq"],
        "B_wo": _B_in["wo"],
    }

def reference(A_x, A_k_cache, A_v_cache, A_wq, A_wo, B_x, B_k_cache, B_v_cache, B_wq, B_wo):
    def _A_ref(x, k_cache, v_cache, wq, wo):
        B, Sq, D = x.shape
        H, Dh = 32, 192
        q = (lambda x, *d: x.permute(*d))((x @ wq).reshape(B, Sq, H, Dh), 0, 2, 1, 3)
        scores = torch.einsum("bhqd,bhkd->bhqk", q, k_cache) * (Dh ** -0.5)
        p = _softmax(scores, axis=-1)
        o = torch.einsum("bhqk,bhkd->bhqd", p, v_cache)
        return (lambda x, *d: x.permute(*d))(o, 0, 2, 1, 3).reshape(B, Sq, H * Dh) @ wo

    def _B_ref(x, k_cache, v_cache, wq, wo):
        B, Sq, D = x.shape
        Hq, Dh = 32, 192
        Hkv = k_cache.shape[1]
        rep = Hq // Hkv
        q = (lambda x, *d: x.permute(*d))((x @ wq).reshape(B, Sq, Hq, Dh), 0, 2, 1, 3)
        k = (lambda x, n, axis: torch.repeat_interleave(x, n, dim=axis))(k_cache, rep, axis=1)
        v = (lambda x, n, axis: torch.repeat_interleave(x, n, dim=axis))(v_cache, rep, axis=1)
        scores = torch.einsum("bhqd,bhkd->bhqk", q, k) * (Dh ** -0.5)
        p = _softmax(scores, axis=-1)
        o = torch.einsum("bhqk,bhkd->bhqd", p, v)
        return (lambda x, *d: x.permute(*d))(o, 0, 2, 1, 3).reshape(B, Sq, Hq * Dh) @ wo

    a = _A_ref(A_x, A_k_cache, A_v_cache, A_wq, A_wo)
    b = _B_ref(B_x, B_k_cache, B_v_cache, B_wq, B_wo)
    return torch.concatenate([a, b], axis=-1)
```

```cpp
#include <cuda_runtime.h>
#include <cuda_bf16.h>
#include <cuda.h>
#include <stdint.h>

namespace {

__device__ __forceinline__ void wgmma_n64_rs_kmaj(float (&d)[32], uint32_t a0, uint32_t a1, uint32_t a2, uint32_t a3, uint64_t db, int scale_d) {
  asm volatile(
      "{\n.reg .pred p;\nsetp.ne.b32 p, %37, 0;\n"
      "wgmma.mma_async.sync.aligned.m64n64k16.f32.bf16.bf16 {"
      "%0, %1, %2, %3, %4, %5, %6, %7, %8, %9, %10, %11, %12, %13, %14, %15, "
      "%16, %17, %18, %19, %20, %21, %22, %23, %24, %25, %26, %27, %28, %29, %30, %31"
      "}, {%32, %33, %34, %35}, %36, p, 1, 1, 0;\n}\n"
      : "+f"(d[0]), "+f"(d[1]), "+f"(d[2]), "+f"(d[3]), "+f"(d[4]), "+f"(d[5]), "+f"(d[6]), "+f"(d[7]),
        "+f"(d[8]), "+f"(d[9]), "+f"(d[10]), "+f"(d[11]), "+f"(d[12]), "+f"(d[13]), "+f"(d[14]), "+f"(d[15]),
        "+f"(d[16]), "+f"(d[17]), "+f"(d[18]), "+f"(d[19]), "+f"(d[20]), "+f"(d[21]), "+f"(d[22]), "+f"(d[23]),
        "+f"(d[24]), "+f"(d[25]), "+f"(d[26]), "+f"(d[27]), "+f"(d[28]), "+f"(d[29]), "+f"(d[30]), "+f"(d[31])
      : "r"(a0), "r"(a1), "r"(a2), "r"(a3), "l"(db), "r"(scale_d));
}
__device__ __forceinline__ void wgmma_n64_rs_nmaj(float (&d)[32], uint32_t a0, uint32_t a1, uint32_t a2, uint32_t a3, uint64_t db, int scale_d) {
  asm volatile(
      "{\n.reg .pred p;\nsetp.ne.b32 p, %37, 0;\n"
      "wgmma.mma_async.sync.aligned.m64n64k16.f32.bf16.bf16 {"
      "%0, %1, %2, %3, %4, %5, %6, %7, %8, %9, %10, %11, %12, %13, %14, %15, "
      "%16, %17, %18, %19, %20, %21, %22, %23, %24, %25, %26, %27, %28, %29, %30, %31"
      "}, {%32, %33, %34, %35}, %36, p, 1, 1, 1;\n}\n"
      : "+f"(d[0]), "+f"(d[1]), "+f"(d[2]), "+f"(d[3]), "+f"(d[4]), "+f"(d[5]), "+f"(d[6]), "+f"(d[7]),
        "+f"(d[8]), "+f"(d[9]), "+f"(d[10]), "+f"(d[11]), "+f"(d[12]), "+f"(d[13]), "+f"(d[14]), "+f"(d[15]),
        "+f"(d[16]), "+f"(d[17]), "+f"(d[18]), "+f"(d[19]), "+f"(d[20]), "+f"(d[21]), "+f"(d[22]), "+f"(d[23]),
        "+f"(d[24]), "+f"(d[25]), "+f"(d[26]), "+f"(d[27]), "+f"(d[28]), "+f"(d[29]), "+f"(d[30]), "+f"(d[31])
      : "r"(a0), "r"(a1), "r"(a2), "r"(a3), "l"(db), "r"(scale_d));
}
__device__ __forceinline__ void wgmma_n192_rs_nmaj(float (&d)[96], uint32_t a0, uint32_t a1, uint32_t a2, uint32_t a3, uint64_t db, int scale_d) {
  asm volatile(
      "{\n.reg .pred p;\nsetp.ne.b32 p, %101, 0;\n"
      "wgmma.mma_async.sync.aligned.m64n192k16.f32.bf16.bf16 {"
      "%0, %1, %2, %3, %4, %5, %6, %7, %8, %9, %10, %11, %12, %13, %14, %15, "
      "%16, %17, %18, %19, %20, %21, %22, %23, %24, %25, %26, %27, %28, %29, %30, %31, "
      "%32, %33, %34, %35, %36, %37, %38, %39, %40, %41, %42, %43, %44, %45, %46, %47, "
      "%48, %49, %50, %51, %52, %53, %54, %55, %56, %57, %58, %59, %60, %61, %62, %63, "
      "%64, %65, %66, %67, %68, %69, %70, %71, %72, %73, %74, %75, %76, %77, %78, %79, "
      "%80, %81, %82, %83, %84, %85, %86, %87, %88, %89, %90, %91, %92, %93, %94, %95"
      "}, {%96, %97, %98, %99}, %100, p, 1, 1, 1;\n}\n"
      : "+f"(d[0]), "+f"(d[1]), "+f"(d[2]), "+f"(d[3]), "+f"(d[4]), "+f"(d[5]), "+f"(d[6]), "+f"(d[7]),
        "+f"(d[8]), "+f"(d[9]), "+f"(d[10]), "+f"(d[11]), "+f"(d[12]), "+f"(d[13]), "+f"(d[14]), "+f"(d[15]),
        "+f"(d[16]), "+f"(d[17]), "+f"(d[18]), "+f"(d[19]), "+f"(d[20]), "+f"(d[21]), "+f"(d[22]), "+f"(d[23]),
        "+f"(d[24]), "+f"(d[25]), "+f"(d[26]), "+f"(d[27]), "+f"(d[28]), "+f"(d[29]), "+f"(d[30]), "+f"(d[31]),
        "+f"(d[32]), "+f"(d[33]), "+f"(d[34]), "+f"(d[35]), "+f"(d[36]), "+f"(d[37]), "+f"(d[38]), "+f"(d[39]),
        "+f"(d[40]), "+f"(d[41]), "+f"(d[42]), "+f"(d[43]), "+f"(d[44]), "+f"(d[45]), "+f"(d[46]), "+f"(d[47]),
        "+f"(d[48]), "+f"(d[49]), "+f"(d[50]), "+f"(d[51]), "+f"(d[52]), "+f"(d[53]), "+f"(d[54]), "+f"(d[55]),
        "+f"(d[56]), "+f"(d[57]), "+f"(d[58]), "+f"(d[59]), "+f"(d[60]), "+f"(d[61]), "+f"(d[62]), "+f"(d[63]),
        "+f"(d[64]), "+f"(d[65]), "+f"(d[66]), "+f"(d[67]), "+f"(d[68]), "+f"(d[69]), "+f"(d[70]), "+f"(d[71]),
        "+f"(d[72]), "+f"(d[73]), "+f"(d[74]), "+f"(d[75]), "+f"(d[76]), "+f"(d[77]), "+f"(d[78]), "+f"(d[79]),
        "+f"(d[80]), "+f"(d[81]), "+f"(d[82]), "+f"(d[83]), "+f"(d[84]), "+f"(d[85]), "+f"(d[86]), "+f"(d[87]),
        "+f"(d[88]), "+f"(d[89]), "+f"(d[90]), "+f"(d[91]), "+f"(d[92]), "+f"(d[93]), "+f"(d[94]), "+f"(d[95])
      : "r"(a0), "r"(a1), "r"(a2), "r"(a3), "l"(db), "r"(scale_d));
}
__device__ __forceinline__ void wgmma_n192_ss_nmaj(float (&d)[96], uint64_t da, uint64_t db, int scale_d) {
  asm volatile(
      "{\n.reg .pred p;\nsetp.ne.b32 p, %98, 0;\n"
      "wgmma.mma_async.sync.aligned.m64n192k16.f32.bf16.bf16 {"
      "%0, %1, %2, %3, %4, %5, %6, %7, %8, %9, %10, %11, %12, %13, %14, %15, "
      "%16, %17, %18, %19, %20, %21, %22, %23, %24, %25, %26, %27, %28, %29, %30, %31, "
      "%32, %33, %34, %35, %36, %37, %38, %39, %40, %41, %42, %43, %44, %45, %46, %47, "
      "%48, %49, %50, %51, %52, %53, %54, %55, %56, %57, %58, %59, %60, %61, %62, %63, "
      "%64, %65, %66, %67, %68, %69, %70, %71, %72, %73, %74, %75, %76, %77, %78, %79, "
      "%80, %81, %82, %83, %84, %85, %86, %87, %88, %89, %90, %91, %92, %93, %94, %95"
      "}, %96, %97, p, 1, 1, 0, 1;\n}\n"
      : "+f"(d[0]), "+f"(d[1]), "+f"(d[2]), "+f"(d[3]), "+f"(d[4]), "+f"(d[5]), "+f"(d[6]), "+f"(d[7]),
        "+f"(d[8]), "+f"(d[9]), "+f"(d[10]), "+f"(d[11]), "+f"(d[12]), "+f"(d[13]), "+f"(d[14]), "+f"(d[15]),
        "+f"(d[16]), "+f"(d[17]), "+f"(d[18]), "+f"(d[19]), "+f"(d[20]), "+f"(d[21]), "+f"(d[22]), "+f"(d[23]),
        "+f"(d[24]), "+f"(d[25]), "+f"(d[26]), "+f"(d[27]), "+f"(d[28]), "+f"(d[29]), "+f"(d[30]), "+f"(d[31]),
        "+f"(d[32]), "+f"(d[33]), "+f"(d[34]), "+f"(d[35]), "+f"(d[36]), "+f"(d[37]), "+f"(d[38]), "+f"(d[39]),
        "+f"(d[40]), "+f"(d[41]), "+f"(d[42]), "+f"(d[43]), "+f"(d[44]), "+f"(d[45]), "+f"(d[46]), "+f"(d[47]),
        "+f"(d[48]), "+f"(d[49]), "+f"(d[50]), "+f"(d[51]), "+f"(d[52]), "+f"(d[53]), "+f"(d[54]), "+f"(d[55]),
        "+f"(d[56]), "+f"(d[57]), "+f"(d[58]), "+f"(d[59]), "+f"(d[60]), "+f"(d[61]), "+f"(d[62]), "+f"(d[63]),
        "+f"(d[64]), "+f"(d[65]), "+f"(d[66]), "+f"(d[67]), "+f"(d[68]), "+f"(d[69]), "+f"(d[70]), "+f"(d[71]),
        "+f"(d[72]), "+f"(d[73]), "+f"(d[74]), "+f"(d[75]), "+f"(d[76]), "+f"(d[77]), "+f"(d[78]), "+f"(d[79]),
        "+f"(d[80]), "+f"(d[81]), "+f"(d[82]), "+f"(d[83]), "+f"(d[84]), "+f"(d[85]), "+f"(d[86]), "+f"(d[87]),
        "+f"(d[88]), "+f"(d[89]), "+f"(d[90]), "+f"(d[91]), "+f"(d[92]), "+f"(d[93]), "+f"(d[94]), "+f"(d[95])
      : "l"(da), "l"(db), "r"(scale_d));
}

constexpr int kNB = 8, kSq = 128, kD = 640, kH = 32, kSk = 1024, kDh = 192;
constexpr int NS = 7;
constexpr uint32_t SLOT = 24576;
constexpr uint32_t STG_OFF = NS * SLOT;
constexpr uint32_t STG_WARP = 6144;
constexpr uint32_t BAR_OFF = STG_OFF + 8 * STG_WARP;
constexpr uint32_t SMEM_BYTES = BAR_OFF + 512 + 1024;
constexpr int NCTA = 128;

struct Sched {
  uint32_t delay_ns[8];
  uint8_t cap2[8][4];
  uint8_t pf0[8];
  uint32_t pf_t0, pf_dt, pf_kb;
  uint32_t conv_delay;
  uint32_t w_t0, w_dt;
  int8_t adj2[4][4];
  int8_t adj[4][4];
};

struct Params {
  CUtensorMap x[2], wq[2], k[2], v[2], wo[2], outm;
  Sched sc;
  const char* xptr0;
  const char* kptr0;
  const char* vptr0;
  const char* wqptr0;
  const char* woptr0;
  __nv_bfloat16* out;
};

constexpr uint32_t AREA_BYTES = 8 * 5 * 8192;
constexpr uint32_t PROBE_OFF = 6 * AREA_BYTES;
__device__ uint4 g_acc_raw[(4 * 2097152) / 16];
__device__ unsigned g_cnt[NCTA];
__device__ unsigned g_claim[8];
__device__ unsigned g_prog[24];

__device__ __forceinline__ uint32_t smem_u32(const void* p) { return (uint32_t)__cvta_generic_to_shared(p); }
__device__ __forceinline__ void mbar_init(uint32_t bar, uint32_t cnt) {
  asm volatile("mbarrier.init.shared::cta.b64 [%0], %1;" ::"r"(bar), "r"(cnt) : "memory");
}
__device__ __forceinline__ void mbar_expect_tx(uint32_t bar, uint32_t bytes) {
  asm volatile("mbarrier.arrive.expect_tx.shared::cta.b64 _, [%0], %1;" ::"r"(bar), "r"(bytes) : "memory");
}
__device__ __forceinline__ void mbar_arrive(uint32_t bar) {
  asm volatile("mbarrier.arrive.shared::cta.b64 _, [%0];" ::"r"(bar) : "memory");
}
__device__ __forceinline__ void mbar_arrive_remote(uint32_t rbar) {
  asm volatile("mbarrier.arrive.shared::cluster.b64 _, [%0];" ::"r"(rbar) : "memory");
}
__device__ __forceinline__ void mbar_wait(uint32_t bar, uint32_t parity) {
  asm volatile(
      "{\n.reg .pred p;\n.reg .u32 t0, t1;\n"
      "mbarrier.try_wait.parity.shared::cta.b64 p, [%0], %1;\n"
      "@p bra WDONE;\n"
      "mov.u32 t0, %%clock;\n"
      "WLOOP:\n"
      "mbarrier.try_wait.parity.shared::cta.b64 p, [%0], %1;\n"
      "@p bra WDONE;\n"
      "mov.u32 t1, %%clock;\n"
      "sub.u32 t1, t1, t0;\n"
      "setp.lt.u32 p, t1, 40000000;\n"
      "@p bra WLOOP;\n"
      "WDONE:\n}\n" ::"r"(bar), "r"(parity) : "memory");
}
__device__ __forceinline__ void mbar_wait_cluster(uint32_t bar, uint32_t parity) {
  asm volatile(
      "{\n.reg .pred p;\n.reg .u32 t0, t1;\n"
      "mov.u32 t0, %%clock;\n"
      "WLOOP:\n"
      "mbarrier.try_wait.parity.acquire.cluster.shared::cta.b64 p, [%0], %1;\n"
      "@p bra WDONE;\n"
      "mov.u32 t1, %%clock;\n"
      "sub.u32 t1, t1, t0;\n"
      "setp.lt.u32 p, t1, 40000000;\n"
      "@p bra WLOOP;\n"
      "WDONE:\n}\n" ::"r"(bar), "r"(parity) : "memory");
}
__device__ __forceinline__ uint32_t mapa(uint32_t addr, uint32_t rank) {
  uint32_t r;
  asm volatile("mapa.shared::cluster.u32 %0, %1, %2;" : "=r"(r) : "r"(addr), "r"(rank));
  return r;
}
__device__ __forceinline__ void tma_2d(uint32_t dst, const CUtensorMap* tm, uint32_t bar, int c0, int c1) {
  asm volatile(
      "cp.async.bulk.tensor.2d.shared::cluster.global.mbarrier::complete_tx::bytes [%0], [%1, {%3, %4}], [%2];" ::"r"(dst),
      "l"(tm), "r"(bar), "r"(c0), "r"(c1)
      : "memory");
}
__device__ __forceinline__ void tma_3d(uint32_t dst, const CUtensorMap* tm, uint32_t bar, int c0, int c1, int c2) {
  asm volatile(
      "cp.async.bulk.tensor.3d.shared::cluster.global.mbarrier::complete_tx::bytes [%0], [%1, {%3, %4, %5}], [%2];" ::"r"(dst),
      "l"(tm), "r"(bar), "r"(c0), "r"(c1), "r"(c2)
      : "memory");
}
__device__ __forceinline__ void tma_3d_hint(uint32_t dst, const CUtensorMap* tm, uint32_t bar, int c0, int c1, int c2,
                                            uint64_t pol) {
  asm volatile(
      "cp.async.bulk.tensor.3d.shared::cluster.global.mbarrier::complete_tx::bytes.L2::cache_hint [%0], [%1, {%3, %4, %5}], "
      "[%2], %6;" ::"r"(dst),
      "l"(tm), "r"(bar), "r"(c0), "r"(c1), "r"(c2), "l"(pol)
      : "memory");
}
__device__ __forceinline__ void l2_prefetch(const void* src, uint32_t bytes, uint64_t pol) {
  asm volatile("cp.async.bulk.prefetch.L2.global.L2::cache_hint [%0], %1, %2;" ::"l"(src), "r"(bytes), "l"(pol) : "memory");
}
__device__ __forceinline__ void l2_prefetch_plain(const void* src, uint32_t bytes) {
  asm volatile("cp.async.bulk.prefetch.L2.global [%0], %1;" ::"l"(src), "r"(bytes) : "memory");
}
__device__ __forceinline__ void l2_prefetch_3d(const CUtensorMap* tm, int c0, int c1, int c2) {
  asm volatile("cp.async.bulk.prefetch.tensor.3d.L2.global.tile [%0, {%1, %2, %3}];" ::"l"(tm), "r"(c0), "r"(c1), "r"(c2)
               : "memory");
}
__device__ __forceinline__ void wg_fence() { asm volatile("wgmma.fence.sync.aligned;" ::: "memory"); }
__device__ __forceinline__ void wg_commit() { asm volatile("wgmma.commit_group.sync.aligned;" ::: "memory"); }
template <int N>
__device__ __forceinline__ void wg_wait() {
  asm volatile("wgmma.wait_group.sync.aligned %0;" ::"n"(N) : "memory");
}
template <int N>
__device__ __forceinline__ void pin(float (&r)[N]) {
#pragma unroll
  for (int i = 0; i < N; i++) asm volatile("" : "+f"(r[i])::"memory");
}
__device__ __forceinline__ uint64_t desc_kmaj(uint32_t addr) {
  return (uint64_t)(((addr >> 4) & 0x3FFF) | (1u << 16)) | ((uint64_t)(64u | (1u << 30)) << 32);
}
__device__ __forceinline__ uint64_t desc_nmaj(uint32_t addr) {
  return (uint64_t)(((addr >> 4) & 0x3FFF) | (512u << 16)) | ((uint64_t)(64u | (1u << 30)) << 32);
}
__device__ __forceinline__ uint32_t pack_bf16(float lo, float hi) {
  uint32_t r;
  asm("cvt.rn.bf16x2.f32 %0, %1, %2;" : "=r"(r) : "f"(hi), "f"(lo));
  return r;
}
__device__ __forceinline__ float ex2(float x) {
  float r;
  asm("ex2.approx.ftz.f32 %0, %1;" : "=f"(r) : "f"(x));
  return r;
}
__device__ __forceinline__ void bar_sync(int id, int n) { asm volatile("bar.sync %0, %1;" ::"r"(id), "r"(n) : "memory"); }
__device__ __forceinline__ void bar_arrive(int id, int n) { asm volatile("bar.arrive %0, %1;" ::"r"(id), "r"(n) : "memory"); }
__device__ __forceinline__ unsigned ld_acquire(const unsigned* p) {
  unsigned v;
  asm volatile("ld.acquire.gpu.global.u32 %0, [%1];" : "=r"(v) : "l"(p) : "memory");
  return v;
}
__device__ __forceinline__ unsigned long long gtime() {
  unsigned long long t;
  asm volatile("mov.u64 %0, %%globaltimer;" : "=l"(t));
  return t;
}

__device__ __forceinline__ char* acc_base() {
  return reinterpret_cast<char*>((reinterpret_cast<uint64_t>(g_acc_raw) + 2097151ull) & ~2097151ull);
}
__device__ __forceinline__ uint32_t acc_off(uint32_t area, uint32_t cw) {
  return (area / 6) * 2097152u + (area % 6) * AREA_BYTES + cw * 5 * 8192;
}
__device__ __forceinline__ uint32_t timed_atom(char* p) {
  uint32_t t0, t1, v;
  asm volatile("mov.u32 %0, %%clock;" : "=r"(t0)::"memory");
  asm volatile("atom.relaxed.gpu.global.add.u32 %0, [%1], 1;" : "=r"(v) : "l"(p) : "memory");
  asm volatile("{\n.reg .pred p;\nsetp.ne.u32 p, %1, 0xffffffff;\nmov.u32 %0, 0;\n@p mov.u32 %0, %%clock;\n}" : "=r"(t1) : "r"(v) : "memory");
  return t1 - t0;
}

struct Ring {
  uint32_t slot, phase;
  __device__ __forceinline__ void advance() {
    if (++slot == NS) { slot = 0; phase ^= 1; }
  }
};

constexpr float kLazy = 8.0f;
template <bool FIRST>
__device__ __forceinline__ bool softmax_step(float (&s)[32], float& m0, float& m1, float& l0, float& l1, float& a0,
                                             float& a1, float c) {
  float x0 = fmaxf(s[0], s[1]), x1 = fmaxf(s[2], s[3]);
#pragma unroll
  for (int j = 1; j < 8; j++) {
    x0 = fmaxf(x0, fmaxf(s[4 * j], s[4 * j + 1]));
    x1 = fmaxf(x1, fmaxf(s[4 * j + 2], s[4 * j + 3]));
  }
  x0 = fmaxf(x0, __shfl_xor_sync(0xffffffffu, x0, 1));
  x1 = fmaxf(x1, __shfl_xor_sync(0xffffffffu, x1, 1));
  x0 = fmaxf(x0, __shfl_xor_sync(0xffffffffu, x0, 2));
  x1 = fmaxf(x1, __shfl_xor_sync(0xffffffffu, x1, 2));
  bool resc = false;
  if (FIRST) {
    m0 = x0;
    m1 = x1;
  } else {
    resc = __any_sync(0xffffffffu, fmaxf(x0 - m0, x1 - m1) * c > kLazy);
    if (resc) {
      const float n0 = fmaxf(m0, x0), n1 = fmaxf(m1, x1);
      a0 = ex2((m0 - n0) * c);
      a1 = ex2((m1 - n1) * c);
      m0 = n0;
      m1 = n1;
      l0 *= a0;
      l1 *= a1;
    }
  }
  const float b0 = -m0 * c, b1 = -m1 * c;
  float r0 = 0.f, r1 = 0.f;
#pragma unroll
  for (int j = 0; j < 8; j++) {
    s[4 * j] = ex2(fmaf(s[4 * j], c, b0));
    s[4 * j + 1] = ex2(fmaf(s[4 * j + 1], c, b0));
    s[4 * j + 2] = ex2(fmaf(s[4 * j + 2], c, b1));
    s[4 * j + 3] = ex2(fmaf(s[4 * j + 3], c, b1));
    r0 += s[4 * j] + s[4 * j + 1];
    r1 += s[4 * j + 2] + s[4 * j + 3];
  }
  l0 += r0;
  l1 += r1;
  return resc;
}

template <int C>
__device__ __forceinline__ void drain(float (&a)[32], uint32_t stg, uint32_t tgt, uint32_t lane, bool last,
                                      const CUtensorMap* outm, int col0) {
  if (C >= 3 && lane == 0) asm volatile("cp.async.bulk.wait_group.read 2;" ::: "memory");
  __syncwarp();
  const uint32_t sp = stg + (C % 3) * 2048;
  const uint32_t ra = sp + (lane & 15) * 128;
#pragma unroll
  for (int jj = 0; jj < 4; jj++)
    asm volatile("stmatrix.sync.aligned.m8n8.x4.shared.b16 [%0], {%1, %2, %3, %4};" ::"r"(ra + (((2 * jj + (lane >> 4)) ^ (lane & 7)) << 4)),
                 "r"(pack_bf16(a[8 * jj], a[8 * jj + 1])), "r"(pack_bf16(a[8 * jj + 2], a[8 * jj + 3])),
                 "r"(pack_bf16(a[8 * jj + 4], a[8 * jj + 5])), "r"(pack_bf16(a[8 * jj + 6], a[8 * jj + 7]))
                 : "memory");
  asm volatile("fence.proxy.async.shared::cta;" ::: "memory");
  __syncwarp();
  if (lane == 0) {
    if (!last) {
      asm volatile("cp.reduce.async.bulk.global.shared::cta.bulk_group.add.noftz.bf16 [%0], [%1], %2;" ::"l"(acc_base() + ((tgt & ~8191u) + C * 8192 + ((tgt >> C) & 1) * 4096)),
                   "r"(sp), "n"(2048)
                   : "memory");
    } else {
      asm volatile("cp.reduce.async.bulk.tensor.2d.global.shared::cta.add.tile.bulk_group [%0, {%2, %3}], [%1];" ::"l"(outm), "r"(sp),
                   "r"(col0 + C * 64), "r"(tgt)
                   : "memory");
    }
    asm volatile("cp.async.bulk.commit_group;" ::: "memory");
  }
  __syncwarp();
}
__device__ __forceinline__ uint32_t add_bf16x2(uint32_t x, uint32_t y) {
  return pack_bf16(__uint_as_float(x << 16) + __uint_as_float(y << 16), __uint_as_float(x & 0xffff0000u) + __uint_as_float(y & 0xffff0000u));
}

__global__ void __cluster_dims__(2, 1, 1) __launch_bounds__(384, 1) fused_attn_kernel(const __grid_constant__ Params P) {
  extern __shared__ uint8_t smem_raw[];
  const uint32_t sbase = (smem_u32(smem_raw) + 1023u) & ~1023u;
  const uint32_t bar_full = sbase + BAR_OFF;
  const uint32_t bar_empty = bar_full + 320;
  const uint32_t bar_xfull = bar_full + 128;
  const uint32_t bar_xready = bar_full + 192;
  const uint32_t bar_rdone = bar_full + 256;
  const uint32_t bar_zok = bar_full + 264;
  const uint32_t bar_item = bar_full + 272;
  const uint32_t s_item = bar_full + 280, s_adj = bar_full + 288, s_tgt = bar_full + 384;

  const uint32_t warp = __shfl_sync(0xffffffffu, threadIdx.x >> 5, 0), lane = threadIdx.x & 31;
  const uint32_t rank = blockIdx.x & 1;
  uint32_t b, hq0;
  {
    const uint32_t i = blockIdx.x >> 1;
    const uint32_t row = i < 4 ? 4 + i : i < 36 ? (i - 4) >> 3 : 4 + (i - 36) / 7;
    hq0 = i < 4 ? 0 : i < 36 ? (i - 4) & 7 : 1 + (i - 36) % 7;
    b = (row >> 1) + 4 * (row & 1);
  }
  const uint32_t cta = (b * 8 + hq0) * 2 + rank;
  const bool late = b >= 4;
  if (threadIdx.x == 0) {
    mbar_init(bar_item, 1);
    asm volatile("fence.mbarrier_init.release.cluster;" ::: "memory");
  } else if (threadIdx.x == 32) {
    for (int i = 0; i < NS; i++) {
      mbar_init(bar_full + 8 * i, 1);
      mbar_init(bar_empty + 8 * i, 8);
    }
    for (int i = 0; i < 8; i++) {
      mbar_init(bar_xfull + 8 * i, 1);
      mbar_init(bar_xready + 8 * i, 1);
    }
    mbar_init(bar_rdone, 8);
    mbar_init(bar_zok, 1);
    asm volatile("st.shared.u32 [%0], %1;" ::"r"(s_adj), "r"(0) : "memory");
    asm volatile("fence.mbarrier_init.release.cluster;" ::: "memory");
  } else if (threadIdx.x == 64) {
    l2_prefetch_plain(P.xptr0 + (size_t)blockIdx.x * 8 * (kD * 2), 8 * kD * 2);
    l2_prefetch_3d(&P.wq[0], 0, (blockIdx.x >> 4) * 64, (blockIdx.x & 15) * 3);
    if (blockIdx.x < 32) l2_prefetch_3d(&P.wq[0], 0, (8 + (blockIdx.x >> 4)) * 64, (blockIdx.x & 15) * 3);
  }
  __syncthreads();
  asm volatile("barrier.cluster.arrive.release.aligned;" ::: "memory");

  if (warp < 4) {
    asm volatile("setmaxnreg.dec.sync.aligned.u32 56;");
    if (warp == 0) {
      if (lane == 0) {
        uint64_t pol;
        asm volatile("createpolicy.fractional.L2::evict_first.b64 %0, 1.0;" : "=l"(pol));
        Ring rg{0, 1};
        auto pf_kv = [&](int t) {
          const size_t row0 = (size_t)(b * kH + 2 * hq0 + rank) * kSk;
          if (t == 0 || (t & 1)) l2_prefetch(P.kptr0 + (row0 + ((t + 1) >> 1) * 64) * 384, SLOT, pol);
          else l2_prefetch(P.vptr0 + (row0 + ((t >> 1) - 1) * 64) * 384, SLOT, pol);
        };
        auto acquire = [&](uint32_t bytes) {
          mbar_wait(bar_empty + 8 * rg.slot, rg.phase);
          mbar_expect_tx(bar_full + 8 * rg.slot, bytes);
        };
        int npf = 0;
        const int pf0 = P.sc.pf0[b];
        {
          const uint32_t dl = P.sc.delay_ns[b];
          const unsigned long long t0 = gtime();
          uint32_t el, nw = late ? 0 : 6;
          while ((el = (uint32_t)(gtime() - t0)) < dl) {
            if (npf < pf0 && el >= P.sc.pf_t0 + npf * P.sc.pf_dt) pf_kv(npf++);
            if (nw < 6 && el >= P.sc.w_t0 + nw * P.sc.w_dt) {
              const uint32_t l = cta - 64;
              if (nw == 2 || nw == 3) {
                for (int i = 0; i < 10; i++) l2_prefetch_plain(P.wqptr0 + (size_t)(l * 10 + i) * 12288 + nw * 3072, 3072);
              } else {
                l2_prefetch_plain(P.woptr0 + (size_t)((nw < 2 ? nw : nw - 2) * 64 + l) * 30720, 30720);
              }
              nw++;
            }
            __nanosleep(100);
          }
        }
        uint32_t hq = hq0;
        for (int r = 0; r < 4; r++) {
          if (r == 1) {
            mbar_wait_cluster(bar_item, 0);
            asm volatile("ld.shared.u32 %0, [%1];" : "=r"(hq) : "r"(s_item) : "memory");
          }
          const int br = r >> 1;
          const int h = 2 * (hq + 8 * (r & 1)) + rank;
          const int row0 = (b * kH + h) * kSk;
          for (int kb = 0; kb < 10; kb++) {
            acquire(16384);
            tma_2d(sbase + rg.slot * SLOT, &P.x[br], bar_full + 8 * rg.slot, kb * 64, b * kSq);
            rg.advance();
            acquire(SLOT);
            tma_3d(sbase + rg.slot * SLOT, &P.wq[br], bar_full + 8 * rg.slot, 0, kb * 64, h * 3);
            rg.advance();
            if (r == 0 && kb >= (int)P.sc.pf_kb && npf < pf0) { pf_kv(npf++); if (kb < 3 && npf < pf0) pf_kv(npf++); }
          }
          const int cap2 = P.sc.cap2[b][r];
          unsigned pos = 0;
          int adjr = 0;
          for (int t = 0; t < 32; t++) {
            const bool isk = (t == 0) || ((t & 1) && t < 31);
            const int j = isk ? (t + 1) >> 1 : (t - 1) >> 1;
            {
              int adj;
              asm volatile("ld.volatile.shared.s32 %0, [%1];" : "=r"(adj) : "r"(s_adj) : "memory");
              if (t == 10 || t == 20) pos = atomicAdd(&g_prog[(t == 10 ? 8 : 16) + (b >> 2) * 4 + r], 1u);
              if (t == 15 || t == 25) {
                adjr = P.sc.adj2[r][(pos >> 4) & 3];
                if (pos == 63) g_prog[(t == 15 ? 8 : 16) + (b >> 2) * 4 + r] = 0;
              }
              if (t >= 15) adj = adjr;
              int s2 = (int)rg.slot - max(min((cap2 + adj + (t & 1)) >> 1, NS - 1), 1);
              uint32_t ph = rg.phase ^ 1;
              if (s2 < 0) { s2 += NS; ph ^= 1; }
              mbar_wait(bar_full + 8 * s2, ph);
            }
            acquire(SLOT);
            tma_3d_hint(sbase + rg.slot * SLOT, isk ? &P.k[br] : &P.v[br], bar_full + 8 * rg.slot, 0, row0 + j * 64, 0, pol);
            rg.advance();
          }
          for (int t = 0; t < 10; t++) {
            const int c = t < 3 ? t : t < 6 ? t - 3 : (t >> 1);
            const int pe = t < 3 ? 0 : t < 6 ? 1 : (t & 1);
            acquire(SLOT);
            tma_2d(sbase + rg.slot * SLOT, &P.wo[br], bar_full + 8 * rg.slot, rank * 320 + c * 64, (h ^ pe) * kDh);
            rg.advance();
          }
        }
      }
      __syncwarp();
      asm volatile("barrier.cluster.wait.acquire.aligned;" ::: "memory");
    } else if (warp == 3) {
      const uint32_t area = b * 2 + rank;
      uint32_t near = 0;
      if (lane == 0) {
        char* pp = acc_base() + (area / 6) * 2097152u + PROBE_OFF + cta * 32;
        for (int i = 0; i < 4; i++) __stcg(reinterpret_cast<uint4*>(pp + (i >> 1) * 4096) + (i & 1), make_uint4(0, 0, 0, 0));
        uint32_t l0 = ~0u, l1 = ~0u;
        for (int i = 0; i < 5; i++) {
          l0 = min(l0, timed_atom(pp));
          l1 = min(l1, timed_atom(pp + 4096));
        }
        near = (l1 < l0 ? 1u : 0u) ^ (__popc(PROBE_OFF & 0xB2000u) & 1u);
      }
      __syncwarp();
      asm volatile("barrier.cluster.wait.acquire.aligned;" ::: "memory");
      if (lane == 0 && rank == 0) {
        uint32_t smid;
        asm("mov.u32 %0, %%smid;" : "=r"(smid));
        const uint32_t t = smid >> 1;
        uint32_t hq = t < 32 ? t & 7 : t < 60 ? 1 + (t - 32) % 7 : 0;
        uint32_t old = atomicOr(&g_claim[b], 1u << hq);
        for (int it = 0; it < 8 && (old >> hq & 1); it++) {
          hq = (__ffs(~old) - 1) & 7;
          old = atomicOr(&g_claim[b], 1u << hq);
        }
        if ((old | 1u << hq) == 255u) g_claim[b] = 0;
        asm volatile("st.shared.u32 [%0], %1;" ::"r"(s_item), "r"(hq) : "memory");
        asm volatile("st.shared::cluster.u32 [%0], %1;" ::"r"(mapa(s_item, 1)), "r"(hq) : "memory");
        mbar_arrive(bar_item);
        asm volatile("mbarrier.arrive.release.cluster.shared::cluster.b64 _, [%0];" ::"r"(mapa(bar_item, 1)) : "memory");
      }
      near = __shfl_sync(0xffffffffu, near, 0);
      if (lane < 8) {
        uint32_t tgt = acc_off(area, lane);
        const uint32_t off = tgt;
        for (int cc = 0; cc < 5; cc++) tgt |= ((__popc((off + cc * 8192) & 0xB2000u) ^ near) & 1) << cc;
        asm volatile("st.shared.u32 [%0], %1;" ::"r"(s_tgt + lane * 4), "r"(tgt) : "memory");
      }
      unsigned* cp = &g_cnt[area * 8 + (lane & 7)];
      for (int r = 0; r < (late ? 4 : 5); r++) {
        mbar_wait(bar_rdone, r & 1);
        if (lane == 8 && r < 4) {
          const unsigned pos = atomicAdd(&g_prog[(b >> 2) * 4 + r], 1u);
          if (pos == 63) g_prog[(b >> 2) * 4 + r] = 0;
          asm volatile("st.volatile.shared.s32 [%0], %1;" ::"r"(s_adj), "r"((int)P.sc.adj[r][(pos >> 4) & 3]) : "memory");
        }
        __syncwarp();
        if (r > 0 && lane < 8) {
          asm volatile("fence.acq_rel.gpu;" ::: "memory");
          asm volatile("red.relaxed.gpu.global.add.u32 [%0], 1;" ::"l"(cp) : "memory");
        }
        if (r == 0 || r == 2 || (r == 3 && late)) {
          if (lane < 8) {
            uint32_t it = 0;
            while (ld_acquire(cp) < (r == 0 ? 1u : r == 2 ? 18u : 27u)) {
              __nanosleep(200);
              if (++it > (1u << 18)) break;
            }
          }
          asm volatile("fence.proxy.async.global;" ::: "memory");
          __syncwarp();
          if (lane == 0) mbar_arrive(bar_zok);
          if (r == 3 && lane < 8 && atomicAdd(cp, 1u) == 34) *cp = 0;
        }
        __syncwarp();
      }
    } else {
      asm volatile("barrier.cluster.wait.acquire.aligned;" ::: "memory");
      const uint32_t t = threadIdx.x - 32;
      uint4* reg = reinterpret_cast<uint4*>(acc_base() + acc_off(cta >> 3, cta & 7));
      for (int st = 0; st < 3; st++) {
        if (st == 0) mbar_wait(bar_rdone, 0);
        if (lane == 0) {
          if (st > 0) {
            uint32_t it = 0;
            while (ld_acquire(&g_cnt[cta]) != (st == 1 ? 17u : late ? 26u : 34u)) {
              __nanosleep(300);
              if (++it > (1u << 17)) break;
            }
          }
          if (st < 2) {
            const unsigned long long t0 = gtime();
            while (gtime() - t0 < (st == 0 ? 7000u : P.sc.conv_delay)) __nanosleep(200);
          }
        }
        __syncwarp();
        if (st > 0) {
          __nv_bfloat16* dst = P.out + (size_t)((cta >> 4) * kSq + (cta & 7) * 16 + (lane >> 3)) * (2 * kD) + (st - 1) * kD +
                               ((cta >> 3) & 1) * 320;
#pragma unroll 1
          for (int g = (warp - 1) * 10; g < warp * 10; g += 5) {
            uint4 u[5], w[5];
#pragma unroll
            for (int i = 0; i < 5; i++) {
              const uint4* s3 = reg + lane + ((g + i) >> 2) * 512 + ((g + i) & 3) * 32;
              u[i] = __ldcg(s3);
              w[i] = __ldcg(s3 + 256);
            }
#pragma unroll
            for (int i = 0; i < 5; i++) {
              const int gg = g + i;
              const uint32_t col = (gg >> 2) * 64 + (((lane & 7) ^ (((gg & 1) << 2) | (lane >> 3))) << 3);
              *reinterpret_cast<uint4*>(dst + (gg & 3) * 4 * (2 * kD) + col) =
                  make_uint4(add_bf16x2(u[i].x, w[i].x), add_bf16x2(u[i].y, w[i].y), add_bf16x2(u[i].z, w[i].z), add_bf16x2(u[i].w, w[i].w));
            }
          }
        }
        if (st < 2) {
          for (int g = (warp - 1) * 10; g < warp * 10; g++) {
            uint4* s3 = reg + lane + (g >> 2) * 512 + (g & 3) * 32;
            __stcg(s3, make_uint4(0, 0, 0, 0));
            __stcg(s3 + 256, make_uint4(0, 0, 0, 0));
          }
        }
        bar_sync(3, 64);
        if (t == 0) {
          if (st == 2 && !late) {
            g_cnt[cta] = 0;
          } else {
            asm volatile("fence.acq_rel.gpu;" ::: "memory");
            asm volatile("red.relaxed.gpu.global.add.u32 [%0], 1;" ::"l"(&g_cnt[cta]) : "memory");
          }
        }
      }
    }
  } else {
    asm volatile("setmaxnreg.inc.sync.aligned.u32 224;");
    asm volatile("barrier.cluster.wait.acquire.aligned;" ::: "memory");
    const uint32_t wg = (warp >> 2) - 1;
    const uint32_t cw = warp - 4;
    const uint32_t stg = sbase + STG_OFF + cw * STG_WARP;
    const float c = 0.07216878364870322f * 1.4426950408889634f;
    Ring rg{0, 0};
    auto release = [&](uint32_t slot) {
      if (lane == 0) mbar_arrive(bar_empty + 8 * slot);
    };
    if (wg == 1) bar_arrive(1, 256);

    float o[96];
    uint32_t q[48];
    auto qstep = [&](int kb) {
      const uint32_t sa = rg.slot;
      mbar_wait(bar_full + 8 * sa, rg.phase);
      rg.advance();
      const uint32_t sb = rg.slot;
      mbar_wait(bar_full + 8 * sb, rg.phase);
      rg.advance();
      const uint64_t da = desc_kmaj(sbase + sa * SLOT + wg * 8192);
      const uint64_t db = desc_nmaj(sbase + sb * SLOT);
      wg_fence();
#pragma unroll
      for (int k = 0; k < 4; k++) wgmma_n192_ss_nmaj(o, da + k * 2, db + k * 128, 1);
      wg_commit();
      if (kb == 4) {
        if (lane == 0) {
          asm volatile("cp.async.bulk.wait_group 0;" ::: "memory");
          mbar_arrive(bar_rdone);
          mbar_expect_tx(bar_xfull + 8 * cw, STG_WARP);
          mbar_arrive_remote(mapa(bar_xready + 8 * cw, rank ^ 1));
        }
        __syncwarp();
      }
      wg_wait<0>();
      release(sa);
      release(sb);
    };
#pragma unroll
    for (int i = 0; i < 96; i++) o[i] = 0.f;
#pragma unroll 1
    for (int kb = 0; kb < 10; kb++) qstep(kb);
    pin(o);
#pragma unroll
    for (int i = 0; i < 48; i++) q[i] = pack_bf16(o[2 * i], o[2 * i + 1]);

#pragma unroll 1
    for (int r = 0; r < 4; r++) {
      float m0, m1, l0 = 0.f, l1 = 0.f, a0 = 1.f, a1 = 1.f;
      {
        float s[32];
        uint32_t p[16];
        {
          const uint32_t sk = rg.slot;
          mbar_wait(bar_full + 8 * sk, rg.phase);
          rg.advance();
          const uint64_t dk = desc_kmaj(sbase + sk * SLOT);
          bar_sync(1 + wg, 256);
          wg_fence();
#pragma unroll
          for (int k = 0; k < 12; k++)
            wgmma_n64_rs_kmaj(s, q[4 * k], q[4 * k + 1], q[4 * k + 2], q[4 * k + 3], dk + (k >> 2) * 512 + (k & 3) * 2, k != 0);
          wg_commit();
          bar_arrive(2 - wg, 256);
          wg_wait<0>();
          pin(s);
          release(sk);
          softmax_step<true>(s, m0, m1, l0, l1, a0, a1, c);
#pragma unroll
          for (int i = 0; i < 16; i++) p[i] = pack_bf16(s[2 * i], s[2 * i + 1]);
        }
#pragma unroll 1
        for (int j = 1; j < 16; j++) {
          const uint32_t sk = rg.slot;
          mbar_wait(bar_full + 8 * sk, rg.phase);
          rg.advance();
          const uint32_t sv = rg.slot;
          const uint32_t pv = rg.phase;
          rg.advance();
          const uint64_t dk = desc_kmaj(sbase + sk * SLOT);
          const uint64_t dv = desc_nmaj(sbase + sv * SLOT);
          bar_sync(1 + wg, 256);
          wg_fence();
#pragma unroll
          for (int k = 0; k < 12; k++)
            wgmma_n64_rs_kmaj(s, q[4 * k], q[4 * k + 1], q[4 * k + 2], q[4 * k + 3], dk + (k >> 2) * 512 + (k & 3) * 2, k != 0);
          wg_commit();
          mbar_wait(bar_full + 8 * sv, pv);
          wg_fence();
#pragma unroll
          for (int k = 0; k < 4; k++)
            wgmma_n192_rs_nmaj(o, p[4 * k], p[4 * k + 1], p[4 * k + 2], p[4 * k + 3], dv + k * 128, (j > 1) | (k != 0));
          wg_commit();
          bar_arrive(2 - wg, 256);
          wg_wait<1>();
          pin(s);
          release(sk);
          const bool resc = softmax_step<false>(s, m0, m1, l0, l1, a0, a1, c);
          wg_wait<0>();
          pin(o);
          release(sv);
#pragma unroll
          for (int i = 0; i < 16; i++) p[i] = pack_bf16(s[2 * i], s[2 * i + 1]);
          if (resc) {
#pragma unroll
            for (int i = 0; i < 24; i++) {
              o[4 * i] *= a0;
              o[4 * i + 1] *= a0;
              o[4 * i + 2] *= a1;
              o[4 * i + 3] *= a1;
            }
          }
        }
        {
          const uint32_t sv = rg.slot;
          mbar_wait(bar_full + 8 * sv, rg.phase);
          rg.advance();
          const uint64_t dv = desc_nmaj(sbase + sv * SLOT);
          wg_fence();
#pragma unroll
          for (int k = 0; k < 4; k++) wgmma_n192_rs_nmaj(o, p[4 * k], p[4 * k + 1], p[4 * k + 2], p[4 * k + 3], dv + k * 128, 1);
          wg_commit();
          l0 += __shfl_xor_sync(0xffffffffu, l0, 1);
          l1 += __shfl_xor_sync(0xffffffffu, l1, 1);
          l0 += __shfl_xor_sync(0xffffffffu, l0, 2);
          l1 += __shfl_xor_sync(0xffffffffu, l1, 2);
          asm("rcp.approx.ftz.f32 %0, %0;" : "+f"(l0));
          asm("rcp.approx.ftz.f32 %0, %0;" : "+f"(l1));
          wg_wait<0>();
          pin(o);
          release(sv);
        }
      }
      float A0[32], A1[32], A2[32];
      {
        uint32_t own[48], oth[48];
        const float i0 = l0, i1 = l1;
#pragma unroll
        for (int i = 0; i < 24; i++) {
          own[2 * i] = pack_bf16(o[4 * i] * i0, o[4 * i + 1] * i0);
          own[2 * i + 1] = pack_bf16(o[4 * i + 2] * i1, o[4 * i + 3] * i1);
        }
        uint32_t s0, s1, s2, s3, s4, s5;
        auto mma12 = [&](float (&acc)[32], uint32_t (&a)[48], uint32_t& slot_out, bool first) {
          slot_out = rg.slot;
          mbar_wait(bar_full + 8 * rg.slot, rg.phase);
          const uint64_t dw = desc_nmaj(sbase + rg.slot * SLOT);
          rg.advance();
          wg_fence();
#pragma unroll
          for (int k = 0; k < 12; k++)
            wgmma_n64_rs_nmaj(acc, a[4 * k], a[4 * k + 1], a[4 * k + 2], a[4 * k + 3], dw + k * 128, !(first && k == 0));
          wg_commit();
        };
        {
          const uint32_t rs = mapa(stg + lane * 16, rank ^ 1);
          const uint32_t rb = mapa(bar_xfull + 8 * cw, rank ^ 1);
          mbar_wait_cluster(bar_xready + 8 * cw, r & 1);
          auto mma12s = [&](float (&acc)[32], uint32_t& slot_out, int j0) {
            slot_out = rg.slot;
            mbar_wait(bar_full + 8 * rg.slot, rg.phase);
            const uint64_t dw = desc_nmaj(sbase + rg.slot * SLOT);
            rg.advance();
            wg_fence();
#pragma unroll
            for (int k = 0; k < 12; k++) {
              wgmma_n64_rs_nmaj(acc, own[4 * k], own[4 * k + 1], own[4 * k + 2], own[4 * k + 3], dw + k * 128, k != 0);
              if (k & 1) {
                const int j = j0 + (k >> 1);
                asm volatile("st.async.shared::cluster.mbarrier::complete_tx::bytes.v4.b32 [%0], {%1, %2, %3, %4}, [%5];" ::"r"(rs + j * 512),
                             "r"(own[4 * j]), "r"(own[4 * j + 1]), "r"(own[4 * j + 2]), "r"(own[4 * j + 3]), "r"(rb)
                             : "memory");
              }
            }
            wg_commit();
          };
          mma12s(A0, s0, 0);
          mma12s(A1, s1, 6);
        }
        mma12(A2, own, s2, true);
        const bool direct = r == 3 && late;
        uint32_t tgt = b * kSq + cw * 16;
        if (lane == 0) {
          if (!(r & 1) || direct) mbar_wait(bar_zok, r == 2);
          if (!direct) asm volatile("ld.shared.u32 %0, [%1];" : "=r"(tgt) : "r"(s_tgt + cw * 4) : "memory");
        }
        __syncwarp();
        wg_wait<2>();
        release(s0);
        wg_wait<1>();
        release(s1);
        mbar_wait_cluster(bar_xfull + 8 * cw, r & 1);
#pragma unroll
        for (int j = 0; j < 12; j++)
          asm volatile("ld.shared.v4.b32 {%0, %1, %2, %3}, [%4];"
                       : "=r"(oth[4 * j]), "=r"(oth[4 * j + 1]), "=r"(oth[4 * j + 2]), "=r"(oth[4 * j + 3])
                       : "r"(stg + j * 512 + lane * 16)
                       : "memory");
        mma12(A0, oth, s3, false);
        wg_wait<1>();
        release(s2);
        mma12(A1, oth, s4, false);
        mma12(A2, oth, s5, false);
        wg_wait<2>();
        pin(A0);
        release(s3);
        drain<0>(A0, stg, tgt, lane, direct, &P.outm, kD + rank * 320);
        mma12(A0, own, s0, true);
        wg_wait<2>();
        pin(A1);
        release(s4);
        drain<1>(A1, stg, tgt, lane, direct, &P.outm, kD + rank * 320);
        mma12(A0, oth, s1, false);
        mma12(A1, own, s2, true);
        wg_wait<3>();
        pin(A2);
        release(s5);
        drain<2>(A2, stg, tgt, lane, direct, &P.outm, kD + rank * 320);
        wg_wait<2>();
        release(s0);
        mma12(A1, oth, s3, false);
        wg_wait<2>();
        pin(A0);
        release(s1);
        drain<3>(A0, stg, tgt, lane, direct, &P.outm, kD + rank * 320);
        wg_wait<1>();
        release(s2);
        wg_wait<0>();
        pin(A1);
        release(s3);
        drain<4>(A1, stg, tgt, lane, direct, &P.outm, kD + rank * 320);
      }
      if (r == 3) break;
#pragma unroll
      for (int i = 0; i < 96; i++) o[i] = 0.f;
#pragma unroll 1
      for (int kb = 0; kb < 10; kb++) qstep(kb);
      pin(o);
#pragma unroll
      for (int i = 0; i < 48; i++) q[i] = pack_bf16(o[2 * i], o[2 * i + 1]);
    }
    if (lane == 0) {
      if (late) {
        asm volatile("cp.async.bulk.wait_group.read 0;" ::: "memory");
      } else {
        asm volatile("cp.async.bulk.wait_group 0;" ::: "memory");
        mbar_arrive(bar_rdone);
      }
    }
  }
}

typedef CUresult (*EncodeFn)(CUtensorMap*, CUtensorMapDataType, cuuint32_t, void*, const cuuint64_t*, const cuuint64_t*,
                             const cuuint32_t*, const cuuint32_t*, CUtensorMapInterleave, CUtensorMapSwizzle,
                             CUtensorMapL2promotion, CUtensorMapFloatOOBfill);

void encode(EncodeFn fn, CUtensorMap* tm, void* base, int rank, const cuuint64_t* dims, const cuuint64_t* strides,
            const cuuint32_t* box) {
  const cuuint32_t es[4] = {1, 1, 1, 1};
  fn(tm, CU_TENSOR_MAP_DATA_TYPE_BFLOAT16, rank, base, dims, strides, box, es, CU_TENSOR_MAP_INTERLEAVE_NONE,
     CU_TENSOR_MAP_SWIZZLE_128B, CU_TENSOR_MAP_L2_PROMOTION_L2_128B, CU_TENSOR_MAP_FLOAT_OOB_FILL_NONE);
}

Sched g_sched = {{0, 0, 0, 0, 12000, 12000, 12000, 12000},
                 {{12, 10, 9, 9}, {12, 10, 9, 9}, {12, 10, 9, 9}, {12, 10, 9, 9}, {8, 8, 7, 7}, {8, 8, 7, 7}, {8, 8, 7, 7}, {8, 8, 7, 7}},
                 {4, 4, 4, 4, 2, 2, 2, 2}, 0, 300, 2, 10000, 2500, 500,
                 {{-1, 0, 1, 2}, {-1, 0, 1, 2}, {-1, 0, 1, 2}, {-1, 0, 1, 2}},
                 {{0, 0, 0, 0}, {-1, -1, 0, 1}, {-1, -1, 0, 1}, {-1, -1, 0, 1}}};

}

extern "C" void kernel_launch(void* const* d_in, const int* in_sizes, int n_in, void* d_out, int out_size) {
  (void)in_sizes; (void)n_in; (void)out_size;
  static EncodeFn fn = nullptr;
  if (!fn) {
    void* p = nullptr;
    cudaDriverEntryPointQueryResult st;
    cudaGetDriverEntryPoint("cuTensorMapEncodeTiled", &p, cudaEnableDefault, &st);
    fn = (EncodeFn)p;
    cudaFuncSetAttribute(fused_attn_kernel, cudaFuncAttributeMaxDynamicSharedMemorySize, SMEM_BYTES);
  }
  Params P;
  for (int br = 0; br < 2; br++) {
    void* x = d_in[5 * br + 0];
    void* k = d_in[5 * br + 1];
    void* v = d_in[5 * br + 2];
    void* wq = d_in[5 * br + 3];
    void* wo = d_in[5 * br + 4];
    {
      const cuuint64_t dims[2] = {kD, kNB * kSq}, str[1] = {kD * 2};
      const cuuint32_t box[2] = {64, 128};
      encode(fn, &P.x[br], x, 2, dims, str, box);
    }
    {
      const cuuint64_t dims[3] = {64, kD, kH * kDh / 64}, str[2] = {kH * kDh * 2, 128};
      const cuuint32_t box[3] = {64, 64, 3};
      encode(fn, &P.wq[br], wq, 3, dims, str, box);
    }
    {
      const cuuint64_t dims[3] = {64, (cuuint64_t)kNB * kH * kSk, 3}, str[2] = {kDh * 2, 128};
      const cuuint32_t box[3] = {64, 64, 3};
      encode(fn, &P.k[br], k, 3, dims, str, box);
      encode(fn, &P.v[br], v, 3, dims, str, box);
    }
    {
      const cuuint64_t dims[2] = {kD, kH * kDh}, str[1] = {kD * 2};
      const cuuint32_t box[2] = {64, 192};
      encode(fn, &P.wo[br], wo, 2, dims, str, box);
    }
  }
  {
    const cuuint64_t dims[2] = {2 * kD, kNB * kSq}, str[1] = {2 * kD * 2};
    const cuuint32_t box[2] = {64, 16};
    encode(fn, &P.outm, d_out, 2, dims, str, box);
  }
  P.xptr0 = (const char*)d_in[0];
  P.kptr0 = (const char*)d_in[1];
  P.vptr0 = (const char*)d_in[2];
  P.wqptr0 = (const char*)d_in[3];
  P.woptr0 = (const char*)d_in[4];
  P.out = (__nv_bfloat16*)d_out;
  P.sc = g_sched;
  fused_attn_kernel<<<NCTA, 384, SMEM_BYTES>>>(P);
}
```
